```python
import torch

def _softmax(x, axis=-1):
    return torch.softmax(x, dim=axis)
def _gelu(x):
    return torch.nn.functional.gelu(x, approximate="tanh")
def _silu(x):
    return torch.nn.functional.silu(x)
def _sigmoid(x):
    return torch.sigmoid(x)
def _layernorm(x, axis=-1, eps=1e-5):
    m = x.mean(dim=axis, keepdim=True)
    v = x.var(dim=axis, keepdim=True, unbiased=False)
    return (x - m) / torch.sqrt(v + eps)
def _scatter_add(tgt, idx, src, axis=0):
    return tgt.clone().index_add_(axis, idx, src)
def _segment_sum(src, seg, n):
    out = torch.zeros((n,) + src.shape[1:], dtype=src.dtype)
    return out.index_add_(0, seg, src)
def _pad(x, pw):
    flat = tuple(v for pair in reversed(pw) for v in pair)
    return torch.nn.functional.pad(x, flat)

kernel_name = 'interleave_layers__grouped_kv_mqa__glu_gated_geglu__prompt'

def setup_inputs():

    _w = (lambda a: (lambda t: t.to(torch.bfloat16) if t.is_floating_point() else t)(torch.as_tensor(a)))
    def _A_setup():
        B, S, D, H = 1, 2048, 448, 16
        Dh = D // H
        return {
            "x": _w((lambda *s: torch.randn(*s, dtype=torch.bfloat16) * 0.05)(B, S, D)),
            "wq": _w((lambda *s: torch.randn(*s, dtype=torch.bfloat16) * 0.05)(D, H * Dh)),
            "wk": _w((lambda *s: torch.randn(*s, dtype=torch.bfloat16) * 0.05)(D, Dh)),
            "wv": _w((lambda *s: torch.randn(*s, dtype=torch.bfloat16) * 0.05)(D, Dh)),
            "wo": _w((lambda *s: torch.randn(*s, dtype=torch.bfloat16) * 0.05)(H * Dh, D)),
        }
    _A_in = _A_setup()

    def _B_setup():
        B, S, Dm, Df = 1, 2048, 448, 1792
        return {
            "x": _w((lambda *s: torch.randn(*s, dtype=torch.bfloat16) * 0.05)(B, S, Dm)),
            "w_gate": _w((lambda *s: torch.randn(*s, dtype=torch.bfloat16) * 0.8)(Dm, Df) * (Dm ** -0.5)),
            "w_up": _w((lambda *s: torch.randn(*s, dtype=torch.bfloat16) * 0.8)(Dm, Df) * (Dm ** -0.5)),
            "w_down": _w((lambda *s: torch.randn(*s, dtype=torch.bfloat16) * 0.8)(Df, Dm) * (Df ** -0.5)),
        }
    _B_in = _B_setup()

    return {
        "A_x": _A_in["x"],
        "A_wq": _A_in["wq"],
        "A_wk": _A_in["wk"],
        "A_wv": _A_in["wv"],
        "A_wo": _A_in["wo"],
        "B_x": _B_in["x"],
        "B_w_gate": _B_in["w_gate"],
        "B_w_up": _B_in["w_up"],
        "B_w_down": _B_in["w_down"],
    }

def reference(A_x, A_wq, A_wk, A_wv, A_wo, B_x, B_w_gate, B_w_up, B_w_down):
    def _A_ref(x, wq, wk, wv, wo):
        B, S, D = x.shape
        H = 16
        Dh = D // H
        q = (lambda x, *d: x.permute(*d))((x @ wq).reshape(B, S, H, Dh), 0, 2, 1, 3)
        k = x @ wk
        v = x @ wv
        scores = torch.einsum("bhqd,bkd->bhqk", q, k) * (Dh ** -0.5)
        p = _softmax(scores, axis=-1)
        o = torch.einsum("bhqk,bkd->bhqd", p, v)
        return (lambda x, *d: x.permute(*d))(o, 0, 2, 1, 3).reshape(B, S, H * Dh) @ wo

    def _B_ref(x, w_gate, w_up, w_down):
        g = torch.einsum("bsd,df->bsf", x, w_gate)
        u = torch.einsum("bsd,df->bsf", x, w_up)
        h = _gelu(g) * u
        return torch.einsum("bsf,fd->bsd", h, w_down)

    x = A_x
    x = x + _A_ref(_layernorm(x, axis=-1), A_wq, A_wk, A_wv, A_wo)
    x = x + _B_ref(_layernorm(x, axis=-1), B_w_gate, B_w_up, B_w_down)
    x = x + _A_ref(_layernorm(x, axis=-1), A_wq, A_wk, A_wv, A_wo)
    x = x + _B_ref(_layernorm(x, axis=-1), B_w_gate, B_w_up, B_w_down)
    return x
```

```cpp
#include <cuda_runtime.h>
#include <cuda_bf16.h>
#include <cuda.h>
#include <stdint.h>

namespace {

constexpr int D_ = 448, DH_ = 28, DF_ = 1792;
constexpr int NCTA = 128, NTHREADS = 512;
constexpr int SLOT = 16384, NSLOT = 13;
constexpr int IMG = 14336;
constexpr int SM_RESID = NSLOT * SLOT;
constexpr int SM_STAT = SM_RESID + IMG;
constexpr int SM_KVST = SM_STAT + 512;
constexpr int SM_BAR = SM_KVST + 2048;
constexpr int SM_TOTAL = SM_BAR + 512;
constexpr int SMEM_BYTES = SM_TOTAL + 1024;
constexpr int SLOT_Q = 7;
constexpr int SLOT_WKV = 8;
constexpr int SLOT_ACT = 12;
constexpr int FFN_SKEW = 1;

__host__ __device__ constexpr bool is_poly(int j) { return (0xEE >> j) & 1; }

__device__ __align__(1024) uint8_t g_kv[2][16 * 16384];
__device__ __align__(1024) uint8_t g_wkv[D_ * 128];
__device__ float g_kn2[2][512];
__device__ __align__(1024) uint8_t g_xn[2][16][7 * 16384];
__device__ __align__(1024) uint8_t g_part[2][16][8][4 * IMG];
__device__ unsigned g_cnt[2 * (16 + 16 + 128) * 32];
__device__ unsigned g_epoch;

__device__ __forceinline__ unsigned* cnt_kv(int L, int g) { return &g_cnt[(L * 160 + g) * 32]; }
__device__ __forceinline__ unsigned* cnt_ag(int L, int g) { return &g_cnt[(L * 160 + 16 + g) * 32]; }
__device__ __forceinline__ unsigned* cnt_rs(int L, int g, int m, int part) { return &g_cnt[(L * 160 + 32 + g * 8 + m * 4 + part) * 32]; }

__device__ __forceinline__ uint32_t s2u(const void* p) { return (uint32_t)__cvta_generic_to_shared(p); }
__device__ __forceinline__ void mbar_init(uint32_t b, int c) { asm volatile("mbarrier.init.shared::cta.b64 [%0], %1;" ::"r"(b), "r"(c)); }
__device__ __forceinline__ void mbar_expect(uint32_t b, uint32_t bytes) { asm volatile("mbarrier.arrive.expect_tx.shared::cta.b64 _, [%0], %1;" ::"r"(b), "r"(bytes) : "memory"); }
__device__ __forceinline__ void mbar_arrive_n(uint32_t b, uint32_t n) { asm volatile("mbarrier.arrive.shared::cta.b64 _, [%0], %1;" ::"r"(b), "r"(n) : "memory"); }
__device__ __forceinline__ void mbar_arrive_elect(uint32_t b) {
  asm volatile("{\n.reg .pred p;\nelect.sync _|p, 0xffffffff;\n@p mbarrier.arrive.shared::cta.b64 _, [%0];\n}" ::"r"(b) : "memory");
}
__device__ __forceinline__ void mbar_arrive(uint32_t b) { asm volatile("mbarrier.arrive.shared::cta.b64 _, [%0];" ::"r"(b) : "memory"); }
__device__ __forceinline__ void mbar_wait(uint32_t b, uint32_t ph) {
  asm volatile(
      "{\n.reg .pred p;\n.reg .u32 n;\nmov.u32 n, 0;\n"
      "WL_%=:\nmbarrier.try_wait.parity.shared::cta.b64 p, [%0], %1;\n@p bra DN_%=;\n"
      "add.u32 n, n, 1;\nsetp.lt.u32 p, n, 0x40000;\n@p bra WL_%=;\nDN_%=:\n}" ::"r"(b), "r"(ph) : "memory");
}
__device__ __forceinline__ uint32_t mapa(uint32_t a, uint32_t rank) { uint32_t r; asm("mapa.shared::cluster.u32 %0, %1, %2;" : "=r"(r) : "r"(a), "r"(rank)); return r; }
__device__ __forceinline__ void mbar_arrive_remote_elect(uint32_t rb) {
  asm volatile("{\n.reg .pred p;\nelect.sync _|p, 0xffffffff;\n@p mbarrier.arrive.relaxed.cluster.shared::cluster.b64 _, [%0];\n}" ::"r"(rb) : "memory");
}
__device__ __forceinline__ void mbar_wait_cluster(uint32_t b, uint32_t ph) {
  asm volatile(
      "{\n.reg .pred p;\n.reg .u32 n;\nmov.u32 n, 0;\n"
      "WL_%=:\nmbarrier.try_wait.parity.acquire.cluster.shared::cta.b64 p, [%0], %1;\n@p bra DN_%=;\n"
      "add.u32 n, n, 1;\nsetp.lt.u32 p, n, 0x40000;\n@p bra WL_%=;\nDN_%=:\n}" ::"r"(b), "r"(ph) : "memory");
}
__device__ __forceinline__ void st_async128(uint32_t a, uint4 v, uint32_t rbar) {
  asm volatile("st.async.weak.shared::cluster.mbarrier::complete_tx::bytes.v4.b32 [%0], {%1,%2,%3,%4}, [%5];" ::"r"(a), "r"(v.x), "r"(v.y), "r"(v.z), "r"(v.w), "r"(rbar) : "memory");
}
__device__ __forceinline__ bool mbar_test(uint32_t b, uint32_t ph) {
  uint32_t ok;
  asm volatile("{\n.reg .pred p;\nmbarrier.test_wait.parity.shared::cta.b64 p, [%1], %2;\nselp.u32 %0, 1, 0, p;\n}" : "=r"(ok) : "r"(b), "r"(ph) : "memory");
  return ok != 0;
}
__device__ __forceinline__ void bulk_g2s(uint32_t dst, const void* src, uint32_t bytes, uint32_t bar) {
  asm volatile("cp.async.bulk.shared::cluster.global.mbarrier::complete_tx::bytes [%0], [%1], %2, [%3];" ::"r"(dst), "l"(src), "r"(bytes), "r"(bar) : "memory");
}
__device__ __forceinline__ void bulk_s2g(void* dst, uint32_t src, uint32_t bytes) {
  asm volatile("cp.async.bulk.global.shared::cta.bulk_group [%0], [%1], %2;" ::"l"(dst), "r"(src), "r"(bytes) : "memory");
}
__device__ __forceinline__ void tma3d(uint32_t dst, const CUtensorMap* tm, int c0, int c1, int c2, uint32_t bar) {
  asm volatile("cp.async.bulk.tensor.3d.shared::cluster.global.mbarrier::complete_tx::bytes [%0], [%1, {%3, %4, %5}], [%2];" ::"r"(dst), "l"(tm), "r"(bar), "r"(c0), "r"(c1), "r"(c2) : "memory");
}
__device__ __forceinline__ void cp_async4(uint32_t dst, const void* src) { asm volatile("cp.async.ca.shared.global [%0], [%1], 4;" ::"r"(dst), "l"(src) : "memory"); }
__device__ __forceinline__ void prefetch_l2(const void* p, uint32_t bytes) { asm volatile("cp.async.bulk.prefetch.L2.global [%0], %1;" ::"l"(p), "r"(bytes) : "memory"); }
__device__ __forceinline__ void fence_async_smem() { asm volatile("fence.proxy.async.shared::cta;" ::: "memory"); }
__device__ __forceinline__ void bar_sync(int id, int n) { asm volatile("bar.sync %0, %1;" ::"r"(id), "r"(n) : "memory"); }
__device__ __forceinline__ void bar_arrive(int id, int n) { asm volatile("bar.arrive %0, %1;" ::"r"(id), "r"(n) : "memory"); }
__device__ __forceinline__ void signal_add(unsigned* p) {
  asm volatile("fence.acq_rel.gpu;\nred.relaxed.gpu.global.add.u32 [%0], 1;" ::"l"(p) : "memory");
}
__device__ __forceinline__ unsigned load_epoch() { unsigned e; asm volatile("ld.relaxed.gpu.global.u32 %0, [%1];" : "=r"(e) : "l"(&g_epoch)); return e; }
__device__ __forceinline__ void wait_cnt(const unsigned* p, unsigned target) {
  unsigned v, n = 0;
  while (true) {
    asm volatile("ld.relaxed.gpu.global.u32 %0, [%1];" : "=r"(v) : "l"(p) : "memory");
    if ((int)(v - target) >= 0) break;
    if (++n > (1u << 16)) break;
  }
}
__device__ __forceinline__ void wg_fence() { asm volatile("wgmma.fence.sync.aligned;" ::: "memory"); }
__device__ __forceinline__ void wg_commit() { asm volatile("wgmma.commit_group.sync.aligned;" ::: "memory"); }
template <int N> __device__ __forceinline__ void wg_wait() { asm volatile("wgmma.wait_group.sync.aligned %0;" ::"n"(N) : "memory"); }
__device__ __forceinline__ uint32_t mk_desc(uint32_t addr, uint32_t lbo) { return ((addr & 0x3FFFF) >> 4) | ((lbo >> 4) << 16); }
template <int N> __device__ __forceinline__ void fence_regs(float (&d)[N]) {
#pragma unroll
  for (int i = 0; i < N; i++) asm volatile("" : "+f"(d[i])::"memory");
}
__device__ __forceinline__ float ex2(float x) { float y; asm("ex2.approx.ftz.f32 %0, %1;" : "=f"(y) : "f"(x)); return y; }
__device__ __forceinline__ float rcp_fast(float x) { float y; asm("rcp.approx.ftz.f32 %0, %1;" : "=f"(y) : "f"(x)); return y; }
__device__ __forceinline__ float rsqrt_fast(float x) { float y; asm("rsqrt.approx.f32 %0, %1;" : "=f"(y) : "f"(x)); return y; }
__device__ __forceinline__ float tanh_fast(float x) { float y; asm("tanh.approx.f32 %0, %1;" : "=f"(y) : "f"(x)); return y; }
__device__ __forceinline__ uint32_t pack_bf16(float lo, float hi) { uint32_t r; asm("cvt.rn.bf16x2.f32 %0, %1, %2;" : "=r"(r) : "f"(hi), "f"(lo)); return r; }
__device__ __forceinline__ float bf_lo(uint32_t v) { return __uint_as_float(v << 16); }
__device__ __forceinline__ float bf_hi(uint32_t v) { return __uint_as_float(v & 0xFFFF0000u); }
__device__ __forceinline__ void stsm_x4_t(uint32_t addr, uint32_t r0, uint32_t r1, uint32_t r2, uint32_t r3) {
  asm volatile("stmatrix.sync.aligned.m8n8.x4.trans.shared.b16 [%0], {%1,%2,%3,%4};" ::"r"(addr), "r"(r0), "r"(r1), "r"(r2), "r"(r3) : "memory");
}
__device__ __forceinline__ void ldsm_x4_t(uint32_t addr, uint32_t& r0, uint32_t& r1, uint32_t& r2, uint32_t& r3) {
  asm volatile("ldmatrix.sync.aligned.m8n8.x4.trans.shared.b16 {%0,%1,%2,%3}, [%4];" : "=r"(r0), "=r"(r1), "=r"(r2), "=r"(r3) : "r"(addr) : "memory");
}
__device__ __forceinline__ void sts32(uint32_t a, uint32_t v) { asm volatile("st.shared.b32 [%0], %1;" ::"r"(a), "r"(v) : "memory"); }
__device__ __forceinline__ void sts64(uint32_t a, uint2 v) { asm volatile("st.shared.v2.b32 [%0], {%1,%2};" ::"r"(a), "r"(v.x), "r"(v.y) : "memory"); }
__device__ __forceinline__ void sts128(uint32_t a, uint4 v) { asm volatile("st.shared.v4.b32 [%0], {%1,%2,%3,%4};" ::"r"(a), "r"(v.x), "r"(v.y), "r"(v.z), "r"(v.w) : "memory"); }
__device__ __forceinline__ uint32_t lds32(uint32_t a) { uint32_t v; asm volatile("ld.shared.b32 %0, [%1];" : "=r"(v) : "r"(a) : "memory"); return v; }
__device__ __forceinline__ uint2 lds64(uint32_t a) { uint2 v; asm volatile("ld.shared.v2.b32 {%0,%1}, [%2];" : "=r"(v.x), "=r"(v.y) : "r"(a) : "memory"); return v; }
__device__ __forceinline__ uint4 lds128(uint32_t a) { uint4 v; asm volatile("ld.shared.v4.b32 {%0,%1,%2,%3}, [%4];" : "=r"(v.x), "=r"(v.y), "=r"(v.z), "=r"(v.w) : "r"(a) : "memory"); return v; }
__device__ __forceinline__ uint4 ldg128_cg(const void* p) { uint4 v; asm volatile("ld.global.cg.v4.b32 {%0,%1,%2,%3}, [%4];" : "=r"(v.x), "=r"(v.y), "=r"(v.z), "=r"(v.w) : "l"(p) : "memory"); return v; }
__device__ __forceinline__ void stg128(void* p, uint4 v) { asm volatile("st.global.v4.b32 [%0], {%1,%2,%3,%4};" ::"l"(p), "r"(v.x), "r"(v.y), "r"(v.z), "r"(v.w) : "memory"); }

__device__ __forceinline__ void wgmma_rs64_bt(float (&d)[32], uint32_t a0, uint32_t a1, uint32_t a2, uint32_t a3, uint32_t descB, int scaleD) {
  asm volatile("{\n.reg .pred p;\n.reg .b64 db;\nsetp.ne.b32 p, %37, 0;\nmov.b64 db, {%36, 0x40000040};\n"
    "wgmma.mma_async.sync.aligned.m64n64k16.f32.bf16.bf16 {%0, %1, %2, %3, %4, %5, %6, %7, %8, %9, %10, %11, %12, %13, %14, %15, %16, %17, %18, %19, %20, %21, %22, %23, %24, %25, %26, %27, %28, %29, %30, %31}, {%32, %33, %34, %35}, db, p, 1, 1, 1;\n}\n"
    : "+f"(d[0]), "+f"(d[1]), "+f"(d[2]), "+f"(d[3]), "+f"(d[4]), "+f"(d[5]), "+f"(d[6]), "+f"(d[7]), "+f"(d[8]), "+f"(d[9]), "+f"(d[10]), "+f"(d[11]), "+f"(d[12]), "+f"(d[13]), "+f"(d[14]), "+f"(d[15]), "+f"(d[16]), "+f"(d[17]), "+f"(d[18]), "+f"(d[19]), "+f"(d[20]), "+f"(d[21]), "+f"(d[22]), "+f"(d[23]), "+f"(d[24]), "+f"(d[25]), "+f"(d[26]), "+f"(d[27]), "+f"(d[28]), "+f"(d[29]), "+f"(d[30]), "+f"(d[31])
    : "r"(a0), "r"(a1), "r"(a2), "r"(a3), "r"(descB), "r"(scaleD));
}
__device__ __forceinline__ void wgmma_ss16_at(float (&d)[8], uint32_t descA, uint32_t descB, int scaleD) {
  asm volatile("{\n.reg .pred p;\n.reg .b64 da, db;\nsetp.ne.b32 p, %10, 0;\nmov.b64 da, {%8, 0x40000040};\nmov.b64 db, {%9, 0x40000040};\n"
    "wgmma.mma_async.sync.aligned.m64n16k16.f32.bf16.bf16 {%0, %1, %2, %3, %4, %5, %6, %7}, da, db, p, 1, 1, 1, 0;\n}\n"
    : "+f"(d[0]), "+f"(d[1]), "+f"(d[2]), "+f"(d[3]), "+f"(d[4]), "+f"(d[5]), "+f"(d[6]), "+f"(d[7])
    : "r"(descA), "r"(descB), "r"(scaleD));
}
__device__ __forceinline__ void wgmma_ss128_bt(float (&d)[64], uint32_t descA, uint32_t descB, int scaleD) {
  asm volatile("{\n.reg .pred p;\n.reg .b64 da, db;\nsetp.ne.b32 p, %66, 0;\nmov.b64 da, {%64, 0x40000040};\nmov.b64 db, {%65, 0x80000020};\n"
    "wgmma.mma_async.sync.aligned.m64n128k16.f32.bf16.bf16 {%0, %1, %2, %3, %4, %5, %6, %7, %8, %9, %10, %11, %12, %13, %14, %15, %16, %17, %18, %19, %20, %21, %22, %23, %24, %25, %26, %27, %28, %29, %30, %31, %32, %33, %34, %35, %36, %37, %38, %39, %40, %41, %42, %43, %44, %45, %46, %47, %48, %49, %50, %51, %52, %53, %54, %55, %56, %57, %58, %59, %60, %61, %62, %63}, da, db, p, 1, 1, 0, 1;\n}\n"
    : "+f"(d[0]), "+f"(d[1]), "+f"(d[2]), "+f"(d[3]), "+f"(d[4]), "+f"(d[5]), "+f"(d[6]), "+f"(d[7]), "+f"(d[8]), "+f"(d[9]), "+f"(d[10]), "+f"(d[11]), "+f"(d[12]), "+f"(d[13]), "+f"(d[14]), "+f"(d[15]), "+f"(d[16]), "+f"(d[17]), "+f"(d[18]), "+f"(d[19]), "+f"(d[20]), "+f"(d[21]), "+f"(d[22]), "+f"(d[23]), "+f"(d[24]), "+f"(d[25]), "+f"(d[26]), "+f"(d[27]), "+f"(d[28]), "+f"(d[29]), "+f"(d[30]), "+f"(d[31]), "+f"(d[32]), "+f"(d[33]), "+f"(d[34]), "+f"(d[35]), "+f"(d[36]), "+f"(d[37]), "+f"(d[38]), "+f"(d[39]), "+f"(d[40]), "+f"(d[41]), "+f"(d[42]), "+f"(d[43]), "+f"(d[44]), "+f"(d[45]), "+f"(d[46]), "+f"(d[47]), "+f"(d[48]), "+f"(d[49]), "+f"(d[50]), "+f"(d[51]), "+f"(d[52]), "+f"(d[53]), "+f"(d[54]), "+f"(d[55]), "+f"(d[56]), "+f"(d[57]), "+f"(d[58]), "+f"(d[59]), "+f"(d[60]), "+f"(d[61]), "+f"(d[62]), "+f"(d[63])
    : "r"(descA), "r"(descB), "r"(scaleD));
}
__device__ __forceinline__ void wgmma_ss192_bt(float (&d)[96], uint32_t descA, uint32_t descB, int scaleD) {
  asm volatile("{\n.reg .pred p;\n.reg .b64 da, db;\nsetp.ne.b32 p, %98, 0;\nmov.b64 da, {%96, 0x40000040};\nmov.b64 db, {%97, 0x80000020};\n"
    "wgmma.mma_async.sync.aligned.m64n192k16.f32.bf16.bf16 {%0, %1, %2, %3, %4, %5, %6, %7, %8, %9, %10, %11, %12, %13, %14, %15, %16, %17, %18, %19, %20, %21, %22, %23, %24, %25, %26, %27, %28, %29, %30, %31, %32, %33, %34, %35, %36, %37, %38, %39, %40, %41, %42, %43, %44, %45, %46, %47, %48, %49, %50, %51, %52, %53, %54, %55, %56, %57, %58, %59, %60, %61, %62, %63, %64, %65, %66, %67, %68, %69, %70, %71, %72, %73, %74, %75, %76, %77, %78, %79, %80, %81, %82, %83, %84, %85, %86, %87, %88, %89, %90, %91, %92, %93, %94, %95}, da, db, p, 1, 1, 0, 1;\n}\n"
    : "+f"(d[0]), "+f"(d[1]), "+f"(d[2]), "+f"(d[3]), "+f"(d[4]), "+f"(d[5]), "+f"(d[6]), "+f"(d[7]), "+f"(d[8]), "+f"(d[9]), "+f"(d[10]), "+f"(d[11]), "+f"(d[12]), "+f"(d[13]), "+f"(d[14]), "+f"(d[15]), "+f"(d[16]), "+f"(d[17]), "+f"(d[18]), "+f"(d[19]), "+f"(d[20]), "+f"(d[21]), "+f"(d[22]), "+f"(d[23]), "+f"(d[24]), "+f"(d[25]), "+f"(d[26]), "+f"(d[27]), "+f"(d[28]), "+f"(d[29]), "+f"(d[30]), "+f"(d[31]), "+f"(d[32]), "+f"(d[33]), "+f"(d[34]), "+f"(d[35]), "+f"(d[36]), "+f"(d[37]), "+f"(d[38]), "+f"(d[39]), "+f"(d[40]), "+f"(d[41]), "+f"(d[42]), "+f"(d[43]), "+f"(d[44]), "+f"(d[45]), "+f"(d[46]), "+f"(d[47]), "+f"(d[48]), "+f"(d[49]), "+f"(d[50]), "+f"(d[51]), "+f"(d[52]), "+f"(d[53]), "+f"(d[54]), "+f"(d[55]), "+f"(d[56]), "+f"(d[57]), "+f"(d[58]), "+f"(d[59]), "+f"(d[60]), "+f"(d[61]), "+f"(d[62]), "+f"(d[63]), "+f"(d[64]), "+f"(d[65]), "+f"(d[66]), "+f"(d[67]), "+f"(d[68]), "+f"(d[69]), "+f"(d[70]), "+f"(d[71]), "+f"(d[72]), "+f"(d[73]), "+f"(d[74]), "+f"(d[75]), "+f"(d[76]), "+f"(d[77]), "+f"(d[78]), "+f"(d[79]), "+f"(d[80]), "+f"(d[81]), "+f"(d[82]), "+f"(d[83]), "+f"(d[84]), "+f"(d[85]), "+f"(d[86]), "+f"(d[87]), "+f"(d[88]), "+f"(d[89]), "+f"(d[90]), "+f"(d[91]), "+f"(d[92]), "+f"(d[93]), "+f"(d[94]), "+f"(d[95])
    : "r"(descA), "r"(descB), "r"(scaleD));
}
__device__ __forceinline__ void wgmma_rs64_bk(float (&d)[32], uint32_t a0, uint32_t a1, uint32_t a2, uint32_t a3, uint64_t descB, int scaleD) {
  asm volatile("{\n.reg .pred p;\nsetp.ne.b32 p, %37, 0;\n"
    "wgmma.mma_async.sync.aligned.m64n64k16.f32.bf16.bf16 {%0, %1, %2, %3, %4, %5, %6, %7, %8, %9, %10, %11, %12, %13, %14, %15, %16, %17, %18, %19, %20, %21, %22, %23, %24, %25, %26, %27, %28, %29, %30, %31}, {%32, %33, %34, %35}, %36, p, 1, 1, 0;\n}\n"
    : "+f"(d[0]), "+f"(d[1]), "+f"(d[2]), "+f"(d[3]), "+f"(d[4]), "+f"(d[5]), "+f"(d[6]), "+f"(d[7]), "+f"(d[8]), "+f"(d[9]), "+f"(d[10]), "+f"(d[11]), "+f"(d[12]), "+f"(d[13]), "+f"(d[14]), "+f"(d[15]), "+f"(d[16]), "+f"(d[17]), "+f"(d[18]), "+f"(d[19]), "+f"(d[20]), "+f"(d[21]), "+f"(d[22]), "+f"(d[23]), "+f"(d[24]), "+f"(d[25]), "+f"(d[26]), "+f"(d[27]), "+f"(d[28]), "+f"(d[29]), "+f"(d[30]), "+f"(d[31])
    : "r"(a0), "r"(a1), "r"(a2), "r"(a3), "l"(descB), "r"(scaleD));
}
__device__ __forceinline__ void wgmma_rs32_bt(float (&d)[16], uint32_t a0, uint32_t a1, uint32_t a2, uint32_t a3, uint64_t descB, int scaleD) {
  asm volatile("{\n.reg .pred p;\nsetp.ne.b32 p, %21, 0;\n"
    "wgmma.mma_async.sync.aligned.m64n32k16.f32.bf16.bf16 {%0, %1, %2, %3, %4, %5, %6, %7, %8, %9, %10, %11, %12, %13, %14, %15}, {%16, %17, %18, %19}, %20, p, 1, 1, 1;\n}\n"
    : "+f"(d[0]), "+f"(d[1]), "+f"(d[2]), "+f"(d[3]), "+f"(d[4]), "+f"(d[5]), "+f"(d[6]), "+f"(d[7]), "+f"(d[8]), "+f"(d[9]), "+f"(d[10]), "+f"(d[11]), "+f"(d[12]), "+f"(d[13]), "+f"(d[14]), "+f"(d[15])
    : "r"(a0), "r"(a1), "r"(a2), "r"(a3), "l"(descB), "r"(scaleD));
}
#define BWAIT(b, p) mbar_wait(b, p)

__device__ __forceinline__ uint32_t img_off(int row, int col) {
  return (uint32_t)((col >> 6) * 2048 + row * 128 + ((((col >> 3) & 7) ^ (row & 7)) << 4) + ((col & 7) << 1));
}

struct PolyC { uint32_t mask; unsigned short c; };
__device__ __forceinline__ PolyC make_polyc() {
  PolyC k;
  asm volatile("mov.b32 %0, 0x007F007F;" : "=r"(k.mask));
  asm volatile("mov.b16 %0, 0x4001;" : "=h"(k.c));
  return k;
}
__device__ __forceinline__ uint32_t poly_pair(float ylo, float yhi, const PolyC& k) {
  uint32_t z, u, m;
  asm("prmt.b32 %0, %1, %2, 0x6521;" : "=r"(z) : "r"(__float_as_uint(ylo)), "r"(__float_as_uint(yhi)));
  asm("lop3.b32 %0, %1, %2, 0x3F803F80, 0xEA;" : "=r"(u) : "r"(z), "r"(k.mask));
  asm("{.reg .b32 cc; mov.b32 cc, {%2,%2}; fma.rn.bf16x2 %0, %1, %1, cc;}" : "=r"(m) : "r"(u), "h"(k.c));
  return m + z - u;
}
__device__ __forceinline__ void softmax_tile(const float (&s)[32], uint32_t (&p)[16], const PolyC& k) {
#pragma unroll
  for (int j = 0; j < 8; j++) {
    if (is_poly(j)) {
      p[2 * j] = poly_pair(s[4 * j], s[4 * j + 1], k);
      p[2 * j + 1] = poly_pair(s[4 * j + 2], s[4 * j + 3], k);
    } else {
      p[2 * j] = pack_bf16(ex2(s[4 * j]), ex2(s[4 * j + 1]));
      p[2 * j + 1] = pack_bf16(ex2(s[4 * j + 2]), ex2(s[4 * j + 3]));
    }
  }
#pragma unroll
  for (int i = 0; i < 16; i++) asm volatile("" : "+r"(p[i])::"memory");
}
__device__ __forceinline__ void issue_S(float (&s)[32], const uint32_t (&q)[8], uint64_t d) {
  wgmma_rs64_bk(s, q[0], q[1], q[2], q[3], d, 0);
  wgmma_rs64_bk(s, q[4], q[5], q[6], q[7], d + 2, 1);
}
__device__ __forceinline__ void issue_PV(float (&o)[16], const uint32_t (&p)[16], uint64_t d, int acc) {
#pragma unroll
  for (int kk = 0; kk < 4; kk++) wgmma_rs32_bt(o, p[4 * kk], p[4 * kk + 1], p[4 * kk + 2], p[4 * kk + 3], d + kk * 64, acc);
}
__device__ __forceinline__ void mma16816(float (&d)[4], uint32_t a0, uint32_t a1, uint32_t a2, uint32_t a3, uint32_t b0, uint32_t b1) {
  asm volatile("mma.sync.aligned.m16n8k16.row.col.f32.bf16.bf16.f32 {%0,%1,%2,%3}, {%4,%5,%6,%7}, {%8,%9}, {%0,%1,%2,%3};"
               : "+f"(d[0]), "+f"(d[1]), "+f"(d[2]), "+f"(d[3]) : "r"(a0), "r"(a1), "r"(a2), "r"(a3), "r"(b0), "r"(b1));
}
__device__ __forceinline__ void slow_attention(const uint32_t (&q)[8], const uint8_t* kv, float (&o)[16], int lane) {
  const int g = lane >> 2, c = lane & 3;
  float oo[4][4], m0 = -INFINITY, m1 = -INFINITY;
#pragma unroll
  for (int j = 0; j < 4; j++) { oo[j][0] = oo[j][1] = oo[j][2] = oo[j][3] = 0.f; }
#pragma unroll 1
  for (int k0 = 0; k0 < 2048; k0 += 16) {
    const uint8_t* blk = kv + (k0 >> 7) * 16384;
    float s[2][4];
#pragma unroll
    for (int h = 0; h < 2; h++) {
      const int r = (k0 & 127) + 8 * h + g, sw = (r >> 1) & 3;
      const uint8_t* row = blk + r * 64 + 4 * c;
      s[h][0] = s[h][1] = s[h][2] = s[h][3] = 0.f;
      mma16816(s[h], q[0], q[1], q[2], q[3], __ldcg((const uint32_t*)(row + ((0 ^ sw) << 4))), __ldcg((const uint32_t*)(row + ((1 ^ sw) << 4))));
      mma16816(s[h], q[4], q[5], q[6], q[7], __ldcg((const uint32_t*)(row + ((2 ^ sw) << 4))), __ldcg((const uint32_t*)(row + ((3 ^ sw) << 4))));
      const float sc = is_poly(((k0 >> 3) + h) & 7) ? (1.f / 128.f) : 1.f;
      s[h][0] *= sc; s[h][1] *= sc; s[h][2] *= sc; s[h][3] *= sc;
    }
    float b0 = fmaxf(fmaxf(s[0][0], s[0][1]), fmaxf(s[1][0], s[1][1])), b1 = fmaxf(fmaxf(s[0][2], s[0][3]), fmaxf(s[1][2], s[1][3]));
    b0 = fmaxf(b0, __shfl_xor_sync(~0u, b0, 1)); b0 = fmaxf(b0, __shfl_xor_sync(~0u, b0, 2));
    b1 = fmaxf(b1, __shfl_xor_sync(~0u, b1, 1)); b1 = fmaxf(b1, __shfl_xor_sync(~0u, b1, 2));
    const float n0 = fmaxf(m0, b0), n1 = fmaxf(m1, b1);
    const float a0 = ex2(m0 - n0), a1 = ex2(m1 - n1);
    m0 = n0; m1 = n1;
    const uint32_t p0 = pack_bf16(ex2(s[0][0] - n0), ex2(s[0][1] - n0)), p1 = pack_bf16(ex2(s[0][2] - n1), ex2(s[0][3] - n1));
    const uint32_t p2 = pack_bf16(ex2(s[1][0] - n0), ex2(s[1][1] - n0)), p3 = pack_bf16(ex2(s[1][2] - n1), ex2(s[1][3] - n1));
#pragma unroll
    for (int j = 0; j < 4; j++) {
      oo[j][0] *= a0; oo[j][1] *= a0; oo[j][2] *= a1; oo[j][3] *= a1;
      uint32_t e[4];
#pragma unroll
      for (int t = 0; t < 4; t++) {
        const int r = (k0 & 127) + 2 * c + (t & 1) + 8 * (t >> 1);
        e[t] = __ldcg((const unsigned short*)(blk + 8192 + r * 64 + ((j ^ ((r >> 1) & 3)) << 4) + 2 * g));
      }
      mma16816(oo[j], p0, p1, p2, p3, e[0] | (e[1] << 16), e[2] | (e[3] << 16));
    }
  }
#pragma unroll
  for (int j = 0; j < 4; j++) { o[4 * j] = oo[j][0]; o[4 * j + 1] = oo[j][1]; o[4 * j + 2] = oo[j][2]; o[4 * j + 3] = oo[j][3]; }
}

__device__ __forceinline__ float gelu_mul(float g, float u) {
  const float t = tanh_fast(g * fmaf(g * g, 0.044715f * 0.7978845608028654f, 0.7978845608028654f));
  const float hg = 0.5f * g;
  return fmaf(hg, t, hg) * u;
}

enum { T_END, T_TMA, T_KV, T_X, T_WKV, T_KVSIG, T_AGWAIT, T_FLIP, T_SIG, T_RS, T_QWAIT, T_RAW };
__constant__ uint32_t c_prog[4][2][40] = {
  {{0x1,0xc0001,0x140001,0x201,0xc0201,0x301,0x20311,0xc0301,0xe0311,0x180301,0x1a0311,0xd00501,0xd40511,0x14c0501,0x1500511,0x1000701,0x1070711,0x8,0x0,0x0,0x0,0x0,0x0,0x0,0x0,0x0,0x0,0x0,0x0,0x0,0x0,0x0,0x0,0x0,0x0,0x0,0x0,0x0,0x0,0x0},
   {0x1,0xc0001,0x140001,0x201,0xc0201,0x301,0x20311,0xc0301,0xe0311,0x180301,0x1a0311,0xd00501,0xd40511,0x14c0501,0x1500511,0x1000701,0x1070711,0x8,0x0,0x0,0x0,0x0,0x0,0x0,0x0,0x0,0x0,0x0,0x0,0x0,0x0,0x0,0x0,0x0,0x0,0x0,0x0,0x0,0x0,0x0},
   },
  {{0x20021,0xe0021,0x160021,0x20221,0xe0221,0x40321,0x60331,0x100321,0x120331,0xc00521,0xc40531,0xd80521,0x1400531,0x1540521,0x1580531,0x1400721,0x1470731,0x0,0x0,0x0,0x0,0x0,0x0,0x0,0x0,0x0,0x0,0x0,0x0,0x0,0x0,0x0,0x0,0x0,0x0,0x0,0x0,0x0,0x0,0x0},
   {0x20021,0xe0021,0x160021,0x20221,0xe0221,0x40321,0x60331,0x100321,0x120331,0xc00521,0xc40531,0xd80521,0x1400531,0x1540521,0x1580531,0x1400721,0x1470731,0x0,0x0,0x0,0x0,0x0,0x0,0x0,0x0,0x0,0x0,0x0,0x0,0x0,0x0,0x0,0x0,0x0,0x0,0x0,0x0,0x0,0x0,0x0},
   },
  {{0x4b,0x106b,0x40041,0x60061,0x100041,0x120061,0x180041,0x1a0061,0x40241,0xa,0x77,0x60261,0x100241,0x120261,0x180261,0x80341,0xa0351,0x6,0x63,0x1073,0x60c3,0x140341,0x160351,0xc80541,0xcc0551,0x1440541,0x1480551,0x761,0x70771,0xc00741,0xc70751,0x1800751,0x1870741,0x69,0x2169,0x0,0x0,0x0,0x0,0x0},
   {0x40041,0x60061,0x100041,0x120061,0x180041,0x1a0061,0x40241,0xa,0x77,0x60261,0x100241,0x120261,0x180261,0x80341,0xa0351,0x6,0xc7,0x63,0x1073,0x60c3,0x140341,0x160351,0xc80541,0xcc0551,0x1440541,0x1480551,0x761,0x70771,0xc00741,0xc70751,0x1800751,0x1870741,0x69,0x2169,0x0,0x0,0x0,0x0,0x0,0x0},
   },
  {{0x80081,0xa00a1,0x5,0x182,0x1192,0x21a2,0x31b2,0x4182,0x5192,0x61a2,0x71b2,0x8182,0x9192,0xa1a2,0xb1b2,0xc182,0xd192,0xe1a2,0xf1b2,0x80281,0xa02a1,0x140281,0x1602a1,0x1a0281,0x6,0x2083,0x3093,0x40a3,0x50b3,0x400781,0x470791,0x8007a1,0x8707b1,0x10a9,0x0,0x0,0x0,0x0,0x0,0x0},
   {0x84,0x1094,0x20a4,0x30b4,0x80081,0xa00a1,0x5,0x182,0x1192,0x21a2,0x31b2,0x4182,0x5192,0x61a2,0x71b2,0x8182,0x9192,0xa1a2,0xb1b2,0xc182,0xd192,0xe1a2,0xf1b2,0x80281,0xa02a1,0x140281,0x1602a1,0x1a0281,0x6,0x2083,0x3093,0x40a3,0x50b3,0x400781,0x470791,0x8007a1,0x8707b1,0x10a9,0x0,0x0},
   },
};

struct Maps { CUtensorMap m[8]; };

struct Params {
  const __nv_bfloat16* x;
  const __nv_bfloat16* wq;
  const __nv_bfloat16* wk;
  const __nv_bfloat16* wv;
  const __nv_bfloat16* wo;
  const __nv_bfloat16* wg;
  const __nv_bfloat16* wu;
  const __nv_bfloat16* wd;
  __nv_bfloat16* out;
};

__global__ void __cluster_dims__(2, 1, 1) __launch_bounds__(NTHREADS, 1)
fused_kernel(const __grid_constant__ Maps maps, const Params prm) {
  extern __shared__ uint8_t smem_raw[];
  const uint32_t smb = (s2u(smem_raw) + 1023u) & ~1023u;
  const int tid = threadIdx.x, lane = tid & 31;
  const int warp_u = __shfl_sync(0xffffffffu, tid >> 5, 0);
  const int wg = warp_u >> 2, w4 = warp_u & 3;
  const int b = blockIdx.x;
  const int crank = b & 1, cl = b >> 1;
  const int fj = 2 * ((cl & 7) >> 1) + crank, fg = 2 * (cl >> 3) + (cl & 1);
  const int tb = fg * 8 + fj;
  auto fullC = [&](int s) { return smb + SM_BAR + s * 8; };
  auto fullH = [&](int s) { return smb + SM_BAR + 128 + s * 8; };
  auto empty = [&](int s) { return smb + SM_BAR + 256 + s * 8; };
  auto slot = [&](int s) { return smb + (uint32_t)s * SLOT; };
  const uint32_t qrdy = smb + SM_BAR + 384;
  const uint32_t kmrdy = smb + SM_BAR + 392, kmval = smb + SM_BAR + 496;
  const uint32_t ordy = smb + SM_BAR + 400;
  const uint32_t kvdone = smb + SM_BAR + 416;
  const uint32_t hdone = smb + SM_BAR + 424;
  const uint32_t rfull = smb + SM_BAR + 104, rempty = smb + SM_BAR + 232, rstart = smb + SM_BAR + 360;

  const int g = lane >> 2, c = lane & 3;
  if (wg == 2) {
    const uint32_t* xr = reinterpret_cast<const uint32_t*>(prm.x + (size_t)(16 * tb + g) * D_ + 16 * w4 + 2 * c);
    const uint32_t ro = smb + SM_RESID + g * 128 + (((2 * w4) ^ g) << 4) + 4 * c;
#pragma unroll
    for (int i = 0; i < 7; i++) {
      cp_async4(ro + i * 2048, xr + 32 * i); cp_async4(ro + 1024 + i * 2048, xr + 4 * D_ + 32 * i);
      cp_async4((ro ^ 16) + i * 2048, xr + 32 * i + 4); cp_async4((ro ^ 16) + 1024 + i * 2048, xr + 4 * D_ + 32 * i + 4);
    }
  }
  if (warp_u == 0 && lane < 12) {
    const void* p = lane == 0 ? (const void*)(prm.x + (size_t)(16 * tb) * D_) : lane == 1 ? (const void*)prm.wk : lane == 2 ? (const void*)prm.wv
                  : lane == 3 ? (const void*)prm.wq : lane == 4 ? (const void*)prm.wo : lane == 5 ? (const void*)(prm.wg + 224 * fj)
                  : lane == 6 ? (const void*)(prm.wu + 224 * fj) : lane == 7 ? (const void*)(prm.wd + (size_t)224 * fj * D_)
                  : lane == 8 ? (const void*)&maps.m[0] : lane == 9 ? (const void*)&maps.m[2] : lane == 10 ? (const void*)&maps.m[3] : (const void*)&maps.m[7];
    if (lane < 8) asm volatile("prefetch.global.L2 [%0];" ::"l"(p));
    else asm volatile("prefetch.tensormap [%0];" ::"l"(p));
  }
  if (wg == 3) {
    const uint32_t own = w4 == 0 ? 0x10u : w4 == 1 ? 0x32u : w4 == 2 ? 0xC7654u : 0xBA98u;
    const int nown = w4 == 2 ? 5 : w4 == 3 ? 4 : 2;
    if (lane < 3 * nown) {
      const int sl = (own >> (4 * (lane / 3))) & 15, kind = lane % 3;
      mbar_init(smb + SM_BAR + kind * 128 + sl * 8, kind == 2 ? 8 : 1);
    } else if (lane >= 16) {
      const int i = lane - 16;
      if (w4 == 0 && i < 8) mbar_init(hdone + 8 * i, 4);
      if (w4 == 1) {
        if (i < 2) { mbar_init(rfull + 8 * i, 1); mbar_init(rempty + 8 * i, 4); mbar_init(ordy + 8 * i, 8); }
        if (i == 2) { mbar_init(rstart, 8); mbar_init(kmrdy, 1); }
      }
      if (w4 == 2 && i == 0) mbar_init(qrdy, 4);
      if (w4 == 3 && i == 0) mbar_init(kvdone, 4);
    }
    asm volatile("fence.mbarrier_init.release.cluster;\nfence.proxy.async.shared::cta;" ::: "memory");
    __syncwarp();
    bar_arrive(0, 512);
  } else {
    bar_sync(0, 512);
  }
  asm volatile("barrier.cluster.arrive.relaxed.aligned;" ::: "memory");
  if (wg < 2) {
    if (lane == 0 && wg == 0) {
      const uint32_t c1 = (D_ * D_ * 2) / NCTA, c2 = (D_ * DF_ * 2) / NCTA;
      if (w4 == 0) prefetch_l2((const uint8_t*)prm.wo + (size_t)b * c1, c1);
      if (w4 == 1) prefetch_l2((const uint8_t*)prm.wg + (size_t)b * c2, c2);
      if (w4 == 2) prefetch_l2((const uint8_t*)prm.wu + (size_t)b * c2, c2);
      if (w4 == 3) prefetch_l2((const uint8_t*)prm.wd + (size_t)b * c2, c2);
    }
  }
  const uint32_t act = slot(SLOT_ACT);

  if (wg == 3) {
    asm volatile("setmaxnreg.dec.sync.aligned.u32 24;");
    const unsigned epoch = load_epoch();
    if (lane == 0) {
      uint32_t pe = 0xFFFFE0FFu;
#pragma unroll 1
      for (int L = 0; L < 2; L++) {
#pragma unroll 1
        for (int pc = 0;; pc++) {
          const uint32_t cmd = c_prog[w4][L][pc];
          const int type = cmd & 15, s = (cmd >> 4) & 15, m = (cmd >> 8) & 15, a = (cmd >> 12) & 1023, bb = cmd >> 22;
          if (type == T_END) break;
          if (type == T_KV) {
            const int kb = (fg + a) & 15;
            const uint32_t bar = fullC(s), dsts = slot(s), eb = empty(s), ep = (pe >> s) & 1u;
            const uint8_t* ksrc = g_kv[L] + kb * SLOT;
            asm volatile("" ::"l"(ksrc), "r"(bar), "r"(dsts), "r"(eb), "r"(ep));
            wait_cnt(cnt_kv(L, kb), (epoch + 1) * 8);
            BWAIT(eb, ep);
            mbar_expect(bar, SLOT);
            bulk_g2s(dsts, ksrc, SLOT, bar);
            pe ^= 1u << s;
          } else if (type <= T_WKV) {
            const bool tma = type == T_TMA, pair = tma && m < 3, dual = tma && (m == 3 || m == 5);
            const uint32_t bytes = !tma ? ((type == T_WKV && a == 3) ? 8192u : 16384u)
                                        : m < 3 ? 28672u : m == 3 ? 6144u : m == 5 ? 8192u : 14336u;
            const uint32_t bar = ((tma && m < 3) || type == T_WKV) ? fullH(s) : fullC(s);
            const int row = a + (m == 7 ? 224 * fj : 0), unit = bb + (dual ? 7 * fj : 0);
            const uint8_t* src = (type == T_X ? g_xn[L][fg] : g_wkv) + a * SLOT;
            const uint32_t dsts = slot(s), eb = empty(s);
            if (pair) BWAIT(eb + 8, (pe >> (s + 1)) & 1u);
            BWAIT(eb, (pe >> s) & 1u);
            mbar_expect(bar, dual ? 2 * bytes : bytes);
            if (tma) {
              tma3d(dsts, &maps.m[m], 0, row, unit, bar);
              if (dual) tma3d(dsts + bytes, &maps.m[m + 1], 0, row, unit, bar);
            } else {
              bulk_g2s(dsts, src, bytes, bar);
            }
            pe ^= (pair ? 3u : 1u) << s;
          } else if (type == T_RS) {
            const uint32_t pb = m ? 24576u : 16384u;
            const uint8_t* src = &g_part[L][fg][fj][0] + a * 16384;
            wait_cnt(cnt_rs(L, fg, fj >> 2, a), (epoch + 1) * 4);
            if (m) BWAIT(empty(s + 1), (pe >> (s + 1)) & 1u);
            BWAIT(empty(s), (pe >> s) & 1u);
            mbar_expect(fullH(s), pb);
            bulk_g2s(slot(s), src, pb, fullH(s));
            pe ^= (m ? 3u : 1u) << s;
          } else if (type == T_RAW) {
            mbar_expect(fullC(s), D_ * DH_ * 2);
            bulk_g2s(slot(s), a ? prm.wv : prm.wk, D_ * DH_ * 2, fullC(s));
            pe ^= 3u << s;
          } else if (type == T_QWAIT) {
            BWAIT(qrdy, L & 1);
          } else if (type == T_FLIP) {
            pe ^= 1u << s;
          } else if (type == T_SIG) {
            int nx = 0;
            while (nx < 2) {
              BWAIT(hdone + (crank * 4 + nx) * 8, L & 1);
              int hi = nx + 1;
              while (hi < 2 && mbar_test(hdone + (crank * 4 + hi) * 8, L & 1)) hi++;
              asm volatile("fence.acq_rel.gpu;" ::: "memory");
              for (int pp = nx; pp < hi; pp++) { asm volatile("red.relaxed.gpu.global.add.u32 [%0], 1;" ::"l"(cnt_rs(L, fg, crank, pp)) : "memory"); }
              nx = hi;
            }
          } else {
            if (type == T_KVSIG) { BWAIT(kvdone, L & 1); signal_add(cnt_kv(L, fg)); }
            else wait_cnt(cnt_ag(L, fg), (epoch + 1) * 8);
          }
        }
      }
    }
  } else if (wg == 2) {
    asm volatile("setmaxnreg.dec.sync.aligned.u32 120;");
    const unsigned epoch = load_epoch();
    uint32_t pf = 0;
    auto cwait = [&](int s) { mbar_wait(fullH(s), (pf >> s) & 1u); pf ^= 1u << s; };
    auto rel2 = [&](int s) { if (lane == 0) mbar_arrive_n(empty(s), 2); };
    const int ht = tid - 256;
    const uint32_t resid = smb + SM_RESID, stat = smb + SM_STAT;
    const uint32_t dact = mk_desc(act, 16), dw0 = mk_desc(smb, 1024);
    const uint32_t st_row = ((lane >> 4) << 3) + (lane & 7);
    const uint32_t st_off = st_row * 128 + (((2 * w4 + ((lane >> 3) & 1)) ^ (st_row & 7)) << 4);
    const uint32_t fo = g * 128 + (((2 * w4) ^ g) << 4) + 4 * c;

#pragma unroll 1
    for (int L = 0; L <= 2; L++) {
      float s0 = 0.f, s1 = 0.f, q0 = 0.f, q1 = 0.f;
      auto acc_stats = [&](uint32_t n0, uint32_t n1, uint32_t n2, uint32_t n3) {
        s0 += (bf_lo(n0) + bf_hi(n0)) + (bf_lo(n2) + bf_hi(n2)); s1 += (bf_lo(n1) + bf_hi(n1)) + (bf_lo(n3) + bf_hi(n3));
        q0 += bf_lo(n0) * bf_lo(n0) + bf_hi(n0) * bf_hi(n0) + bf_lo(n2) * bf_lo(n2) + bf_hi(n2) * bf_hi(n2);
        q1 += bf_lo(n1) * bf_lo(n1) + bf_hi(n1) * bf_hi(n1) + bf_lo(n3) * bf_lo(n3) + bf_hi(n3) * bf_hi(n3);
      };
      auto put = [&](int i, uint32_t n0, uint32_t n1, uint32_t n2, uint32_t n3) {
        sts32(resid + fo + i * 2048, n0); sts32(resid + fo + 1024 + i * 2048, n1);
        sts32(resid + (fo ^ 16) + i * 2048, n2); sts32(resid + (fo ^ 16) + 1024 + i * 2048, n3);
        acc_stats(n0, n1, n2, n3);
      };
      if (L == 0) {
        asm volatile("cp.async.wait_all;" ::: "memory");
#pragma unroll
        for (int i = 0; i < 7; i++)
          acc_stats(lds32(resid + fo + i * 2048), lds32(resid + fo + 1024 + i * 2048), lds32(resid + (fo ^ 16) + i * 2048), lds32(resid + (fo ^ 16) + 1024 + i * 2048));
      } else {
        uint32_t* orow = reinterpret_cast<uint32_t*>(prm.out + (size_t)(16 * tb + g) * D_ + 16 * w4 + 2 * c);
#pragma unroll 1
        for (int i = 0; i < 7; i++) {
          const int s = (i == 2 || i == 3) ? 10 : 6;
          const uint32_t pb = i < 4 ? 4096u : 6144u;
          if (i == 0 || i == 2 || i == 4) cwait(s);
          const uint32_t pa = slot(s) + (i < 4 ? (i & 1) : i - 4) * 2048 + w4 * 512 + lane * 16;
          float a[8];
#pragma unroll
          for (int e = 0; e < 8; e++) a[e] = 0.f;
#pragma unroll
          for (int k = 0; k < 4; k++) {
            const uint4 v = lds128(pa + k * pb);
            a[0] += bf_lo(v.x); a[1] += bf_hi(v.x); a[2] += bf_lo(v.y); a[3] += bf_hi(v.y);
            a[4] += bf_lo(v.z); a[5] += bf_hi(v.z); a[6] += bf_lo(v.w); a[7] += bf_hi(v.w);
          }
          __syncwarp();
          if (i == 1 || i == 3 || i == 6) { rel2(s); if (i == 6) rel2(s + 1); }
          const uint32_t r0 = lds32(resid + fo + i * 2048), r1 = lds32(resid + fo + 1024 + i * 2048);
          const uint32_t r2 = lds32(resid + (fo ^ 16) + i * 2048), r3 = lds32(resid + (fo ^ 16) + 1024 + i * 2048);
          const uint32_t n0 = pack_bf16(bf_lo(r0) + a[0], bf_hi(r0) + a[1]), n1 = pack_bf16(bf_lo(r1) + a[2], bf_hi(r1) + a[3]);
          const uint32_t n2 = pack_bf16(bf_lo(r2) + a[4], bf_hi(r2) + a[5]), n3 = pack_bf16(bf_lo(r3) + a[6], bf_hi(r3) + a[7]);
          if (L == 2) { orow[32 * i] = n0; orow[4 * D_ + 32 * i] = n1; orow[32 * i + 4] = n2; orow[4 * D_ + 32 * i + 4] = n3; }
          else put(i, n0, n1, n2, n3);
        }
        if (L == 2) { break; }
        BWAIT(hdone + 3 * 8, (L - 1) & 1); BWAIT(hdone + 7 * 8, (L - 1) & 1);
      }
      {
        s0 += __shfl_xor_sync(~0u, s0, 1); q0 += __shfl_xor_sync(~0u, q0, 1); s1 += __shfl_xor_sync(~0u, s1, 1); q1 += __shfl_xor_sync(~0u, q1, 1);
        s0 += __shfl_xor_sync(~0u, s0, 2); q0 += __shfl_xor_sync(~0u, q0, 2); s1 += __shfl_xor_sync(~0u, s1, 2); q1 += __shfl_xor_sync(~0u, q1, 2);
        if (c == 0) {
          sts64(stat + (g * 4 + w4) * 8, make_uint2(__float_as_uint(s0), __float_as_uint(q0)));
          sts64(stat + ((g + 8) * 4 + w4) * 8, make_uint2(__float_as_uint(s1), __float_as_uint(q1)));
        }
        bar_sync(1, 128);
        const uint2 pa = lds64(stat + (g * 4 + c) * 8), pb = lds64(stat + ((g + 8) * 4 + c) * 8);
        float m0 = __uint_as_float(pa.x), v0 = __uint_as_float(pa.y), m1 = __uint_as_float(pb.x), v1 = __uint_as_float(pb.y);
        m0 += __shfl_xor_sync(~0u, m0, 1); v0 += __shfl_xor_sync(~0u, v0, 1); m1 += __shfl_xor_sync(~0u, m1, 1); v1 += __shfl_xor_sync(~0u, v1, 1);
        m0 += __shfl_xor_sync(~0u, m0, 2); v0 += __shfl_xor_sync(~0u, v0, 2); m1 += __shfl_xor_sync(~0u, m1, 2); v1 += __shfl_xor_sync(~0u, v1, 2);
        m0 *= (1.f / D_); m1 *= (1.f / D_);
        const float r0 = rsqrt_fast(fmaxf(v0 * (1.f / D_) - m0 * m0, 0.f) + 1e-5f), r1 = rsqrt_fast(fmaxf(v1 * (1.f / D_) - m1 * m1, 0.f) + 1e-5f);
        const float o0 = -m0 * r0, o1 = -m1 * r1;
#pragma unroll
        for (int i = 0; i < 7; i++) {
          const uint32_t n0 = lds32(resid + fo + i * 2048), n1 = lds32(resid + fo + 1024 + i * 2048);
          const uint32_t n2 = lds32(resid + (fo ^ 16) + i * 2048), n3 = lds32(resid + (fo ^ 16) + 1024 + i * 2048);
          sts32(act + fo + i * 2048, pack_bf16(fmaf(bf_lo(n0), r0, o0), fmaf(bf_hi(n0), r0, o0)));
          sts32(act + fo + 1024 + i * 2048, pack_bf16(fmaf(bf_lo(n1), r1, o1), fmaf(bf_hi(n1), r1, o1)));
          sts32(act + (fo ^ 16) + i * 2048, pack_bf16(fmaf(bf_lo(n2), r0, o0), fmaf(bf_hi(n2), r0, o0)));
          sts32(act + (fo ^ 16) + 1024 + i * 2048, pack_bf16(fmaf(bf_lo(n3), r1, o1), fmaf(bf_hi(n3), r1, o1)));
        }
        fence_async_smem();
        if (L == 0) bar_sync(5, 384); else bar_sync(1, 128);
      }

      float acc[7][8];
#pragma unroll
      for (int u = 0; u < 7; u++) {
#pragma unroll
        for (int e = 0; e < 8; e++) acc[u][e] = 0.f;
        fence_regs(acc[u]);
      }
      if (L == 1) { cwait(11); cwait(10); cwait(9); cwait(8); }
      else if (b == 0 && ht == 0) { bulk_s2g(g_wkv, slot(SLOT_WKV), D_ * 128); asm volatile("cp.async.bulk.commit_group;" ::: "memory"); }
      {
        const uint32_t dw = dw0 + (SLOT_WKV << 10);
#pragma unroll 1
        for (int kb = 0; kb < 7; kb++) {
          wg_fence();
#pragma unroll
          for (int ks = 0; ks < 4; ks++) wgmma_ss16_at(acc[ks], dw + (uint32_t)(kb * 512 + ks * 128), dact + (uint32_t)(kb * 128 + ks * 2), 1);
        }
        wg_commit();
        wg_wait<0>();
#pragma unroll
        for (int u = 0; u < 4; u++) fence_regs(acc[u]);
        if (L == 0 && b == 0 && ht == 0) { asm volatile("cp.async.bulk.wait_group 0;" ::: "memory"); }
        __syncwarp();
        rel2(8); rel2(9); rel2(10); rel2(11);
#pragma unroll
        for (int e = 0; e < 8; e++) acc[0][e] = (acc[0][e] + acc[1][e]) + (acc[2][e] + acc[3][e]);
        const uint32_t kvst = smb + SM_KVST;
        stsm_x4_t(kvst + st_off, pack_bf16(acc[0][0], acc[0][1]), pack_bf16(acc[0][2], acc[0][3]), pack_bf16(acc[0][4], acc[0][5]), pack_bf16(acc[0][6], acc[0][7]));
        bar_sync(1, 128);
        const int isv = ht >> 6, tok = (ht & 63) >> 2, ch = ht & 3;
        const int key = 16 * tb + tok, r = key & 127;
        const bool poly = is_poly((key & 63) >> 3);
        const int o0 = isv * 56 + 16 * ch, o1 = o0 + 8;
        const uint2 lo = lds64(kvst + tok * 128 + (((o0 >> 4) ^ (tok & 7)) << 4) + (o0 & 15));
        const uint2 hi = lds64(kvst + tok * 128 + (((o1 >> 4) ^ (tok & 7)) << 4) + (o1 & 15));
        uint32_t v[4] = {lo.x, lo.y, ch == 3 ? 0u : hi.x, ch == 3 ? 0u : hi.y};
        float n2 = 0.f;
#pragma unroll
        for (int e = 0; e < 4; e++) n2 += bf_lo(v[e]) * bf_lo(v[e]) + bf_hi(v[e]) * bf_hi(v[e]);
        n2 += __shfl_xor_sync(~0u, n2, 1); n2 += __shfl_xor_sync(~0u, n2, 2);
        n2 = (n2 <= 3.0e38f) ? n2 : INFINITY;
        n2 = fmaxf(n2, __shfl_xor_sync(~0u, n2, 4)); n2 = fmaxf(n2, __shfl_xor_sync(~0u, n2, 8)); n2 = fmaxf(n2, __shfl_xor_sync(~0u, n2, 16));
        if (lane == 0) g_kn2[L][b * 4 + w4] = isv ? (n2 <= 1.0e12f ? 0.f : INFINITY) : n2;
        const float ksc = (poly && !isv) ? 128.f : 1.f;
#pragma unroll
        for (int e = 0; e < 4; e++) v[e] = pack_bf16(bf_lo(v[e]) * ksc, bf_hi(v[e]) * ksc);
        if (ch == 3) {
          v[2] = isv ? pack_bf16(1.f, 0.f) : (poly ? pack_bf16(49152.f, -332.f) : 0u);
          v[3] = (poly && !isv) ? pack_bf16(0.734375f, 0.f) : 0u;
        }
        stg128(g_kv[L] + (key >> 7) * 16384 + isv * 8192 + r * 64 + ((ch ^ ((r >> 1) & 3)) << 4), make_uint4(v[0], v[1], v[2], v[3]));
        __syncwarp();
        if (lane == 0) mbar_arrive(kvdone);
      }

#pragma unroll 1
      for (int pass = 0; pass < 2; pass++) {
#pragma unroll
        for (int u = 0; u < 7; u++) {
#pragma unroll
          for (int e = 0; e < 8; e++) acc[u][e] = 0.f;
          fence_regs(acc[u]);
        }
        if (pass == 1) { BWAIT(ordy, L & 1); }
        const unsigned long long tab = pass == 0 ? 0x32103210543210ull : 0x43543210543210ull;
        int sprev = 0;
#pragma unroll 1
        for (int T = 0; T < 14; T++) {
          const int s = (int)((tab >> (4 * T)) & 15) * 2;
          cwait(s);
          const uint32_t dw = dw0 + (uint32_t)(s << 10), db = dact + (uint32_t)((T >> 1) * 128 + (T & 1) * 4);
          wg_fence();
#pragma unroll
          for (int ks = 0; ks < 2; ks++) {
#pragma unroll
            for (int u = 0; u < 7; u++) wgmma_ss16_at(acc[u], dw + ks * 128 + u * 256, db + ks * 2, 1);
          }
          wg_commit();
          wg_wait<1>();
          if (T > 0) { rel2(sprev); rel2(sprev + 1); }
          sprev = s;
        }
        wg_wait<0>();
        rel2(sprev); rel2(sprev + 1);
        if (pass == 1) break;
#pragma unroll
        for (int u = 0; u < 7; u++) fence_regs(acc[u]);
        const float qs = 0.18898223650461362f * 1.4426950408889634f;
#pragma unroll
        for (int u = 0; u < 7; u++)
          stsm_x4_t(slot(SLOT_Q) + u * 2048 + st_off, pack_bf16(acc[u][0] * qs, acc[u][1] * qs), pack_bf16(acc[u][2] * qs, acc[u][3] * qs),
                    pack_bf16(acc[u][4] * qs, acc[u][5] * qs), pack_bf16(acc[u][6] * qs, acc[u][7] * qs));
        __syncwarp();
        if (lane == 0) mbar_arrive(qrdy);
        if (w4 == 0) {
          if (lane < 16) wait_cnt(cnt_kv(L, lane), (epoch + 1) * 8);
          __syncwarp();
          float km = 0.f;
#pragma unroll
          for (int i = 0; i < 4; i++) {
            const uint4 kn = ldg128_cg(&g_kn2[L][lane * 16 + 4 * i]);
            km = fmaxf(km, fmaxf(fmaxf(__uint_as_float(kn.x), __uint_as_float(kn.y)), fmaxf(__uint_as_float(kn.z), __uint_as_float(kn.w))));
          }
#pragma unroll
          for (int of = 16; of > 0; of >>= 1) km = fmaxf(km, __shfl_xor_sync(~0u, km, of));
          if (lane == 0) { sts32(kmval, __float_as_uint(km)); mbar_arrive(kmrdy); }
        }
      }
#pragma unroll
      for (int u = 0; u < 7; u++) fence_regs(acc[u]);
      {
        float s4[4] = {0.f, 0.f, 0.f, 0.f}, q4[4] = {0.f, 0.f, 0.f, 0.f};
#pragma unroll
        for (int u = 0; u < 7; u++) {
          uint32_t r[4];
          ldsm_x4_t(resid + u * 2048 + st_off, r[0], r[1], r[2], r[3]);
#pragma unroll
          for (int m = 0; m < 4; m++) {
            r[m] = pack_bf16(bf_lo(r[m]) + acc[u][2 * m], bf_hi(r[m]) + acc[u][2 * m + 1]);
            acc[u][2 * m] = bf_lo(r[m]); acc[u][2 * m + 1] = bf_hi(r[m]);
            s4[(m >> 1) * 2] += acc[u][2 * m]; s4[(m >> 1) * 2 + 1] += acc[u][2 * m + 1];
            q4[(m >> 1) * 2] += acc[u][2 * m] * acc[u][2 * m]; q4[(m >> 1) * 2 + 1] += acc[u][2 * m + 1] * acc[u][2 * m + 1];
          }
          stsm_x4_t(resid + u * 2048 + st_off, r[0], r[1], r[2], r[3]);
        }
#pragma unroll
        for (int o = 4; o <= 16; o <<= 1) {
#pragma unroll
          for (int e = 0; e < 4; e++) { s4[e] += __shfl_xor_sync(~0u, s4[e], o); q4[e] += __shfl_xor_sync(~0u, q4[e], o); }
        }
        if (g == 0) {
#pragma unroll
          for (int e = 0; e < 4; e++) sts64(stat + (((e >> 1) * 8 + 2 * c + (e & 1)) * 4 + w4) * 8, make_uint2(__float_as_uint(s4[e]), __float_as_uint(q4[e])));
        }
        bar_sync(1, 128);
        float rs[4], of[4];
#pragma unroll
        for (int e = 0; e < 4; e++) {
          const uint4 p01 = lds128(stat + (((e >> 1) * 8 + 2 * c + (e & 1)) * 4) * 8), p23 = lds128(stat + (((e >> 1) * 8 + 2 * c + (e & 1)) * 4 + 2) * 8);
          const float mean = (__uint_as_float(p01.x) + __uint_as_float(p01.z) + __uint_as_float(p23.x) + __uint_as_float(p23.z)) * (1.f / D_);
          const float v = (__uint_as_float(p01.y) + __uint_as_float(p01.w) + __uint_as_float(p23.y) + __uint_as_float(p23.w)) * (1.f / D_);
          rs[e] = rsqrt_fast(fmaxf(v - mean * mean, 0.f) + 1e-5f);
          of[e] = -mean * rs[e];
        }
#pragma unroll
        for (int u = 0; u < 7; u++)
          stsm_x4_t(act + u * 2048 + st_off, pack_bf16(fmaf(acc[u][0], rs[0], of[0]), fmaf(acc[u][1], rs[1], of[1])),
                    pack_bf16(fmaf(acc[u][2], rs[0], of[0]), fmaf(acc[u][3], rs[1], of[1])),
                    pack_bf16(fmaf(acc[u][4], rs[2], of[2]), fmaf(acc[u][5], rs[3], of[3])),
                    pack_bf16(fmaf(acc[u][6], rs[2], of[2]), fmaf(acc[u][7], rs[3], of[3])));
        fence_async_smem();
        bar_sync(1, 128);
        if (w4 == 0) {
          if (lane < 7) {
            bulk_s2g(g_xn[L][fg] + lane * SLOT + fj * 2048, act + lane * 2048, 2048);
            asm volatile("cp.async.bulk.commit_group;" ::: "memory");
            asm volatile("cp.async.bulk.wait_group 0;" ::: "memory");
          }
          __syncwarp();
          if (lane == 0) signal_add(cnt_ag(L, fg));
          if (lane < 8) mbar_arrive(empty(SLOT_ACT));
        }
      }
    }
    if (b == 0 && ht == 0) asm volatile("st.relaxed.gpu.global.u32 [%0], %1;" ::"l"(&g_epoch), "r"(epoch + 1) : "memory");
  } else {
    asm volatile("setmaxnreg.inc.sync.aligned.u32 184;");
    uint32_t pf = 0;
    auto cwait = [&](int s) { mbar_wait(fullC(s), (pf >> s) & 1u); pf ^= 1u << s; };
    auto crelease = [&](int s) { mbar_arrive_elect(empty(s)); };
    const PolyC pk = make_polyc();
    const uint64_t dkv = (uint64_t)mk_desc(smb, 16) | (0x80000020ull << 32);
    {
      const uint32_t wkv = slot(SLOT_WKV);
      for (int k = tid; k < D_; k += 256) sts128(wkv + k * 128 + ((7 ^ (k & 7)) << 4), make_uint4(0, 0, 0, 0));
      cwait(4); cwait(6);
#pragma unroll 5
      for (int q = tid; q < 6400; q += 256) {
        if (q < 6272) {
          const int hv = q >= 3136, qq = q - hv * 3136, k = (qq * 9363) >> 16, off = 56 * hv + 8 * (qq - 7 * k);
          sts64(wkv + k * 128 + (((off >> 4) ^ (k & 7)) << 4) + (off & 15), lds64(slot(4 + 2 * hv) + qq * 8));
        }
      }
      __syncwarp();
      crelease(4); crelease(5); crelease(6); crelease(7);
      fence_async_smem();
      bar_arrive(5, 384);
      asm volatile("barrier.cluster.wait.acquire.aligned;" ::: "memory");
    }

#pragma unroll 1
    for (int L = 0; L < 2; L++) {
      {
        uint32_t qA[8], qB[8], qoA[4], qoB[4];
        float nA0 = 0.f, nA1 = 0.f, nB0 = 0.f, nB1 = 0.f;
        float oA[16], oB[16], sA[32], sB[32];
        uint32_t pA[16], pB[16];
#pragma unroll
        for (int i = 0; i < 16; i++) { oA[i] = 0.f; oB[i] = 0.f; }
#pragma unroll
        for (int i = 0; i < 32; i++) { sA[i] = 0.f; sB[i] = 0.f; }
        fence_regs(oA); fence_regs(oB); fence_regs(sA); fence_regs(sB);
        const int hA = 8 * wg + w4, hB = hA + 4;
#pragma unroll
        for (int i = 0; i < 4; i++) { const int d = 8 * i + 2 * c, dd = d < DH_ ? d : 0; qoA[i] = img_off(g, hA * DH_ + dd); qoB[i] = img_off(g, hB * DH_ + dd); }
        BWAIT(qrdy, L & 1);
        {
          const uint32_t qst = slot(SLOT_Q);
#pragma unroll
          for (int i = 0; i < 4; i++) {
            const bool ok = 8 * i + 2 * c < DH_;
            const int r0 = 4 * (i >> 1) + 2 * (i & 1);
            const uint32_t a0 = ok ? lds32(qst + qoA[i]) : 0u, a1 = ok ? lds32(qst + qoA[i] + 1024) : 0u;
            const uint32_t b0 = ok ? lds32(qst + qoB[i]) : 0u, b1 = ok ? lds32(qst + qoB[i] + 1024) : 0u;
            qA[r0] = a0; qA[r0 + 1] = a1; qB[r0] = b0; qB[r0 + 1] = b1;
            nA0 += bf_lo(a0) * bf_lo(a0) + bf_hi(a0) * bf_hi(a0); nA1 += bf_lo(a1) * bf_lo(a1) + bf_hi(a1) * bf_hi(a1);
            nB0 += bf_lo(b0) * bf_lo(b0) + bf_hi(b0) * bf_hi(b0); nB1 += bf_lo(b1) * bf_lo(b1) + bf_hi(b1) * bf_hi(b1);
          }
          if (c >= 2) { qA[6] = c == 2 ? 0x3F803F80u : 0x00003F80u; qA[7] = qA[6]; qB[6] = qA[6]; qB[7] = qA[6]; }
          __syncwarp();
          crelease(SLOT_Q);
        }
#pragma unroll
        for (int of = 1; of <= 2; of <<= 1) {
          nA0 += __shfl_xor_sync(~0u, nA0, of); nA1 += __shfl_xor_sync(~0u, nA1, of);
          nB0 += __shfl_xor_sync(~0u, nB0, of); nB1 += __shfl_xor_sync(~0u, nB1, of);
        }
        float nmax = fmaxf(fmaxf(nA0, nA1), fmaxf(nB0, nB1));
        if (!(nA0 + nA1 + nB0 + nB1 < INFINITY)) nmax = INFINITY;
        BWAIT(fullC(8), 0);
        wg_fence();
        issue_S(sA, qA, dkv + (8 << 10)); wg_commit();
        issue_S(sB, qB, dkv + (8 << 10)); wg_commit();
        wg_wait<1>(); fence_regs(sA);
        softmax_tile(sA, pA, pk);
        wg_wait<0>(); fence_regs(sB);
        softmax_tile(sB, pB, pk);
#pragma unroll 1
        for (int it = 0; it < 8; it++) {
          const int sa = 8 + 2 * (it & 1), sn = 8 + 2 * ((it + 1) & 1);
          const uint64_t da = dkv + (uint64_t)(sa << 10), dn = it == 7 ? da : dkv + (uint64_t)(sn << 10);
          const uint32_t par = (it >> 1) & 1, parn = ((it + 1) >> 1) & 1;
#pragma unroll
          for (int u = 0; u < 4; u++) {
            const uint64_t nxt = u == 0 ? da + 256 : u == 1 ? da + 1024 : u == 2 ? da + 1024 + 256 : dn;
            const uint64_t cur = da + (u >> 1) * 1024 + (u & 1) * 256 + 512;
            if (u > 0) { wg_wait<1>(); fence_regs(sA); softmax_tile(sA, pA, pk); }
            if (u == 1) BWAIT(fullC(sa + 1), par);
            if (u == 3 && it < 7) BWAIT(fullC(sn), parn);
            wg_fence();
            issue_S(sA, qA, nxt);
            issue_PV(oA, pA, cur, 1);
            wg_commit();
            if (u > 0) { wg_wait<1>(); fence_regs(sB); softmax_tile(sB, pB, pk); wg_fence(); }
            if (u == 2) crelease(sa);
            issue_S(sB, qB, nxt);
            issue_PV(oB, pB, cur, 1);
            wg_commit();
          }
          wg_wait<1>(); fence_regs(sA);
          softmax_tile(sA, pA, pk);
          wg_wait<0>(); fence_regs(sB);
          softmax_tile(sB, pB, pk);
          crelease(sa + 1);
        }
        fence_regs(oA); fence_regs(oB);
        BWAIT(kmrdy, L & 1);
        const float km = __uint_as_float(lds32(kmval));
        const bool unsafe = !(nmax * km <= 8100.f);
        if (__builtin_expect(__any_sync(~0u, unsafe), 0)) {
#pragma unroll 1
          for (int t = 0; t < 2; t++) {
            uint32_t qz[8];
            float oz[16];
#pragma unroll
            for (int i = 0; i < 8; i++) qz[i] = (i >= 6 && c >= 2) ? 0u : (t ? qB[i] : qA[i]);
            slow_attention(qz, g_kv[L], oz, lane);
#pragma unroll
            for (int i = 0; i < 16; i++) { if (t) oB[i] = oz[i]; else oA[i] = oz[i]; }
          }
        }
        const int src = (lane & ~3) | 2;
        const float iA0 = rcp_fast(__shfl_sync(~0u, oA[12], src)), iA1 = rcp_fast(__shfl_sync(~0u, oA[14], src));
        const float iB0 = rcp_fast(__shfl_sync(~0u, oB[12], src)), iB1 = rcp_fast(__shfl_sync(~0u, oB[14], src));
#pragma unroll
        for (int j = 0; j < 4; j++) {
          if (8 * j + 2 * c < DH_) {
            sts32(act + qoA[j], pack_bf16(oA[4 * j] * iA0, oA[4 * j + 1] * iA0));
            sts32(act + qoA[j] + 1024, pack_bf16(oA[4 * j + 2] * iA1, oA[4 * j + 3] * iA1));
            sts32(act + qoB[j], pack_bf16(oB[4 * j] * iB0, oB[4 * j + 1] * iB0));
            sts32(act + qoB[j] + 1024, pack_bf16(oB[4 * j + 2] * iB1, oB[4 * j + 3] * iB1));
          }
        }
        fence_async_smem();
        __syncwarp();
        if (lane == 0) mbar_arrive(ordy);
      }

      uint32_t h[56];
      const uint32_t dax = mk_desc(slot(6) + wg * 8192, 16);
      if (wg == 1) bar_sync(4, 256);
      int ws = 0, wprev = 0;
      {
        float a1[96];
#pragma unroll
        for (int i = 0; i < 96; i++) a1[i] = 0.f;
        fence_regs(a1);
        const uint32_t dbw = mk_desc(smb, 2048);
#pragma unroll 1
        for (int i = 0; i < 14; i++) {
          if (!(i & 1)) cwait(6 + (i >> 1));
          cwait(ws);
          const uint32_t da = dax + (uint32_t)((i >> 1) * (SLOT >> 4) + (i & 1) * 4), db = dbw + (uint32_t)(ws * (SLOT >> 4));
          wg_fence();
          wgmma_ss192_bt(a1, da, db, 1);
          wgmma_ss192_bt(a1, da + 2, db + 64, 1);
          wg_commit();
          if (i == FFN_SKEW && wg == 0) bar_arrive(4, 256);
          wg_wait<1>();
          if (i > 0) crelease(wprev);
          wprev = ws; ws = (ws == 5) ? 0 : ws + 1;
        }
        wg_wait<0>();
        crelease(wprev);
        fence_regs(a1);
#pragma unroll
        for (int jb = 0; jb < 12; jb++) {
          h[2 * jb] = pack_bf16(gelu_mul(a1[4 * jb], a1[48 + 4 * jb]), gelu_mul(a1[4 * jb + 1], a1[48 + 4 * jb + 1]));
          h[2 * jb + 1] = pack_bf16(gelu_mul(a1[4 * jb + 2], a1[48 + 4 * jb + 2]), gelu_mul(a1[4 * jb + 3], a1[48 + 4 * jb + 3]));
        }
      }
#pragma unroll
      for (int i = 24; i < 56; i++) h[i] = 0u;
#pragma unroll 1
      for (int cb = 0; cb < 2; cb++) {
        float a2[64];
#pragma unroll
        for (int i = 0; i < 64; i++) a2[i] = 0.f;
        fence_regs(a2);
        const uint32_t dbw = mk_desc(smb, 4096);
#pragma unroll 1
        for (int i = 0; i < 7; i++) {
          cwait(ws);
          const uint32_t da = dax + (uint32_t)(i * (SLOT >> 4)), db = dbw + (uint32_t)(ws * (SLOT >> 4));
          wg_fence();
#pragma unroll
          for (int ks = 0; ks < 4; ks++) wgmma_ss128_bt(a2, da + ks * 2, db + ks * 64, 1);
          wg_commit();
          wg_wait<1>();
          if (i > 0) { crelease(wprev); if (cb == 1) crelease(6 + i - 1); }
          wprev = ws; ws = (ws == 5) ? 0 : ws + 1;
        }
        wg_wait<0>();
        crelease(wprev);
        if (cb == 1) { crelease(12); mbar_arrive_remote_elect(mapa(rstart, crank ^ 1)); }
        fence_regs(a2);
#pragma unroll
        for (int i = 0; i < 16; i++) h[24 + i] = h[40 + i];
#pragma unroll
        for (int jb = 0; jb < 8; jb++) {
          h[40 + 2 * jb] = pack_bf16(gelu_mul(a2[4 * jb], a2[32 + 4 * jb]), gelu_mul(a2[4 * jb + 1], a2[32 + 4 * jb + 1]));
          h[40 + 2 * jb + 1] = pack_bf16(gelu_mul(a2[4 * jb + 2], a2[32 + 4 * jb + 2]), gelu_mul(a2[4 * jb + 3], a2[32 + 4 * jb + 3]));
        }
      }
      {
        const bool keeper = wg == crank;
        uint8_t* dst = &g_part[L][fg][4 * wg + w4][0] + lane * 16;
        const uint32_t rbuf = slot(SLOT_ACT) + w4 * 2048 + lane * 16, rbuf_peer = mapa(rbuf, crank ^ 1);
        const uint32_t rfull_peer = mapa(rfull, crank ^ 1), rempty_peer = mapa(rempty, crank ^ 1);
        const uint32_t dbd = mk_desc(smb, 1024);
        float d0[32], d1[32];
        uint32_t held[16];
#pragma unroll
        for (int i = 0; i < 32; i++) { d0[i] = 0.f; d1[i] = 0.f; }
        fence_regs(d0); fence_regs(d1);
        auto issue_chunk = [&](float (&d)[32], const int s0, const int s1) {
          cwait(s0); cwait(s1);
          const uint32_t b0 = dbd + s0 * (SLOT >> 4), b1 = dbd + s1 * (SLOT >> 4);
          wg_fence();
#pragma unroll
          for (int k = 0; k < 7; k++) wgmma_rs64_bt(d, h[4 * k], h[4 * k + 1], h[4 * k + 2], h[4 * k + 3], b0 + k * 128, k > 0);
#pragma unroll
          for (int k = 0; k < 7; k++) wgmma_rs64_bt(d, h[28 + 4 * k], h[28 + 4 * k + 1], h[28 + 4 * k + 2], h[28 + 4 * k + 3], b1 + k * 128, 1);
          wg_commit();
        };
        auto send_chunk = [&](const float (&d)[32], const int cidx) {
          const int bf = cidx & 1, k = cidx >> 1;
          if (cidx == 0) mbar_wait_cluster(rstart, L & 1);
          if (cidx >= 2) mbar_wait_cluster(rempty + bf * 8, bf == 0 ? ((L + k - 1) & 1) : ((k - 1) & 1));
#pragma unroll
          for (int qq = 0; qq < 4; qq++)
            st_async128(rbuf_peer + bf * 8192 + qq * 512, make_uint4(pack_bf16(d[8 * qq], d[8 * qq + 1]), pack_bf16(d[8 * qq + 2], d[8 * qq + 3]),
                                                                      pack_bf16(d[8 * qq + 4], d[8 * qq + 5]), pack_bf16(d[8 * qq + 6], d[8 * qq + 7])), rfull_peer + bf * 8);
        };
        auto hold_chunk = [&](const float (&d)[32]) {
#pragma unroll
          for (int i = 0; i < 16; i++) held[i] = pack_bf16(d[2 * i], d[2 * i + 1]);
        };
        auto keep_chunk = [&](const int cidx) {
          const int bf = cidx & 1, k = cidx >> 1;
          if ((tid & 127) == 0) mbar_expect(rfull + bf * 8, 8192);
          mbar_wait_cluster(rfull + bf * 8, bf == 0 ? (k & 1) : ((L + k) & 1));
          uint4 v[4];
#pragma unroll
          for (int qq = 0; qq < 4; qq++) v[qq] = lds128(rbuf + bf * 8192 + qq * 512);
          asm volatile("" ::"r"(v[0].x), "r"(v[1].x), "r"(v[2].x), "r"(v[3].x) : "memory");
          __syncwarp();
          if (cidx < 5) mbar_arrive_remote_elect(rempty_peer + bf * 8);
          auto add2 = [](uint32_t x, uint32_t y) { return pack_bf16(bf_lo(x) + bf_lo(y), bf_hi(x) + bf_hi(y)); };
#pragma unroll
          for (int qq = 0; qq < 4; qq++)
            stg128(dst + (cidx < 4 ? (cidx >> 1) * 16384 + (fj >> 1) * 4096 + (cidx & 1) * 2048 : 32768 + (fj >> 1) * 6144 + (cidx - 4) * 2048) + qq * 512,
                   make_uint4(add2(held[4 * qq], v[qq].x), add2(held[4 * qq + 1], v[qq].y), add2(held[4 * qq + 2], v[qq].z), add2(held[4 * qq + 3], v[qq].w)));
          if (cidx == 1 || cidx == 3 || cidx == 6) { __syncwarp(); if (lane == 0) mbar_arrive(hdone + (wg * 4 + (cidx >> 1)) * 8); }
        };
#define DS0(cc) ((cc) < 3 ? 6 + 2 * (cc) : (cc) == 3 ? 4 : (cc) == 4 ? 0 : (cc) == 5 ? 2 : 5)
#define DS1(cc) ((cc) == 6 ? 4 : DS0(cc) + 1)
#define DACC(i) (((i) & 1) ? d1 : d0)
        issue_chunk(d0, DS0(0), DS1(0));
#pragma unroll
        for (int cc = 1; cc < 7; cc++) {
          issue_chunk(DACC(cc), DS0(cc), DS1(cc));
          wg_wait<1>(); fence_regs(DACC(cc - 1));
          crelease(DS0(cc - 1)); crelease(DS1(cc - 1));
          if (!keeper) send_chunk(DACC(cc - 1), cc - 1);
          else {
            if (cc >= 2) keep_chunk(cc - 2);
            hold_chunk(DACC(cc - 1));
          }
        }
        wg_wait<0>(); fence_regs(d0);
        crelease(DS0(6)); crelease(DS1(6));
        if (keeper) keep_chunk(5);
        if (!keeper) {
          send_chunk(d0, 6);
          if (lane == 0) { mbar_arrive(hdone + (wg * 4 + 3) * 8); }
        } else {
          hold_chunk(d0);
          keep_chunk(6);
          bar_sync(2 + wg, 128);
          if ((tid & 127) == 0) signal_add(cnt_rs(L, fg, wg, 2));
        }
      }
    }
  }
}

typedef CUresult (*EncodeFn)(CUtensorMap*, CUtensorMapDataType, cuuint32_t, void*, const cuuint64_t*, const cuuint64_t*, const cuuint32_t*,
                             const cuuint32_t*, CUtensorMapInterleave, CUtensorMapSwizzle, CUtensorMapL2promotion, CUtensorMapFloatOOBfill);

void make_map(EncodeFn enc, CUtensorMap* tm, const void* base, int rank, const cuuint64_t* dims, const cuuint64_t* strides, const cuuint32_t* box,
              CUtensorMapSwizzle swz) {
  cuuint32_t es[3] = {1, 1, 1};
  enc(tm, CU_TENSOR_MAP_DATA_TYPE_BFLOAT16, (cuuint32_t)rank, const_cast<void*>(base), dims, strides, box, es, CU_TENSOR_MAP_INTERLEAVE_NONE, swz,
      CU_TENSOR_MAP_L2_PROMOTION_L2_256B, CU_TENSOR_MAP_FLOAT_OOB_FILL_NONE);
}

}

extern "C" void kernel_launch(void* const* d_in, const int* in_sizes, int n_in, void* d_out, int out_size) {
  (void)in_sizes; (void)n_in; (void)out_size;
  static EncodeFn enc = nullptr;
  if (!enc) {
    void* fn = nullptr;
    cudaDriverEntryPointQueryResult qr;
    cudaGetDriverEntryPoint("cuTensorMapEncodeTiled", &fn, cudaEnableDefault, &qr);
    enc = (EncodeFn)fn;
    cudaFuncSetAttribute(fused_kernel, cudaFuncAttributeMaxDynamicSharedMemorySize, SMEM_BYTES);
  }
  const __nv_bfloat16* x = (const __nv_bfloat16*)d_in[0];
  const __nv_bfloat16* wq = (const __nv_bfloat16*)d_in[1];
  const __nv_bfloat16* wk = (const __nv_bfloat16*)d_in[2];
  const __nv_bfloat16* wv = (const __nv_bfloat16*)d_in[3];
  const __nv_bfloat16* wo = (const __nv_bfloat16*)d_in[4];
  const __nv_bfloat16* wg = (const __nv_bfloat16*)d_in[6];
  const __nv_bfloat16* wu = (const __nv_bfloat16*)d_in[7];
  const __nv_bfloat16* wd = (const __nv_bfloat16*)d_in[8];
  Maps maps;
  {
    cuuint64_t dims[3] = {64, (cuuint64_t)D_, 7}, str[2] = {(cuuint64_t)D_ * 2, 128};
    cuuint32_t bo[3] = {64, 32, 7};
    make_map(enc, &maps.m[0], wq, 3, dims, str, bo, CU_TENSOR_MAP_SWIZZLE_128B);
    maps.m[1] = maps.m[0];
    make_map(enc, &maps.m[2], wo, 3, dims, str, bo, CU_TENSOR_MAP_SWIZZLE_128B);
  }
  {
    cuuint64_t dims[3] = {32, (cuuint64_t)D_, 56}, str[2] = {(cuuint64_t)DF_ * 2, 64};
    cuuint32_t box2[3] = {32, 64, 2}, box3[3] = {32, 32, 3};
    make_map(enc, &maps.m[3], wg, 3, dims, str, box3, CU_TENSOR_MAP_SWIZZLE_64B);
    make_map(enc, &maps.m[4], wu, 3, dims, str, box3, CU_TENSOR_MAP_SWIZZLE_64B);
    make_map(enc, &maps.m[5], wg, 3, dims, str, box2, CU_TENSOR_MAP_SWIZZLE_64B);
    make_map(enc, &maps.m[6], wu, 3, dims, str, box2, CU_TENSOR_MAP_SWIZZLE_64B);
  }
  {
    cuuint64_t dims[3] = {64, (cuuint64_t)DF_, 7}, str[2] = {(cuuint64_t)D_ * 2, 128};
    cuuint32_t box[3] = {64, 112, 1};
    make_map(enc, &maps.m[7], wd, 3, dims, str, box, CU_TENSOR_MAP_SWIZZLE_128B);
  }
  Params prm{x, wq, wk, wv, wo, wg, wu, wd, (__nv_bfloat16*)d_out};
  fused_kernel<<<NCTA, NTHREADS, SMEM_BYTES, cudaStreamPerThread>>>(maps, prm);
}
```
